```python
import torch

def _softmax(x, axis=-1):
    return torch.softmax(x, dim=axis)
def _gelu(x):
    return torch.nn.functional.gelu(x, approximate="tanh")
def _silu(x):
    return torch.nn.functional.silu(x)
def _sigmoid(x):
    return torch.sigmoid(x)
def _layernorm(x, axis=-1, eps=1e-5):
    m = x.mean(dim=axis, keepdim=True)
    v = x.var(dim=axis, keepdim=True, unbiased=False)
    return (x - m) / torch.sqrt(v + eps)
def _scatter_add(tgt, idx, src, axis=0):
    return tgt.clone().index_add_(axis, idx, src)
def _segment_sum(src, seg, n):
    out = torch.zeros((n,) + src.shape[1:], dtype=src.dtype)
    return out.index_add_(0, seg, src)
def _pad(x, pw):
    flat = tuple(v for pair in reversed(pw) for v in pair)
    return torch.nn.functional.pad(x, flat)

kernel_name = 'interleave_layers__sliding_block__mixer_channel_mlp__prompt'

def setup_inputs():

    _w = (lambda a: (lambda t: t.to(torch.bfloat16) if t.is_floating_point() else t)(torch.as_tensor(a)))
    def _A_setup():
        B, S, D = 1, 2048, 640
        return {
            "x": _w((lambda *s: torch.randn(*s, dtype=torch.bfloat16) * 0.05)(B, S, D)),
            "wqkv": _w((lambda *s: torch.randn(*s, dtype=torch.bfloat16) * 0.05)(D, 3 * D)),
            "wo": _w((lambda *s: torch.randn(*s, dtype=torch.bfloat16) * 0.05)(D, D)),
        }
    _A_in = _A_setup()

    def _B_setup():
        B, S, D, F = 1, 2048, 640, 1728
        return {
            "x": _w((lambda *s: torch.randn(*s, dtype=torch.bfloat16) * 0.05)(B, S, D)),
            "w1": _w((lambda *s: torch.randn(*s, dtype=torch.bfloat16) * 1.6)(D, F) * (D ** -0.5)),
            "b1": _w((lambda *s: torch.randn(*s, dtype=torch.bfloat16) * 1.6)(F)),
            "w2": _w((lambda *s: torch.randn(*s, dtype=torch.bfloat16) * 0.4)(F, D) * (F ** -0.5)),
            "b2": _w((lambda *s: torch.randn(*s, dtype=torch.bfloat16) * 0.4)(D)),
        }
    _B_in = _B_setup()

    return {
        "A_x": _A_in["x"],
        "A_wqkv": _A_in["wqkv"],
        "A_wo": _A_in["wo"],
        "B_x": _B_in["x"],
        "B_w1": _B_in["w1"],
        "B_b1": _B_in["b1"],
        "B_w2": _B_in["w2"],
        "B_b2": _B_in["b2"],
    }

def reference(A_x, A_wqkv, A_wo, B_x, B_w1, B_b1, B_w2, B_b2):
    def _A_ref(x, wqkv, wo):
        B, S, D = x.shape
        H = 32; Dh = D // H; W = 256
        qkv = (lambda x, *d: x.permute(*d))((x @ wqkv).reshape(B, S, 3, H, Dh), 2, 0, 3, 1, 4)
        q, k, v = qkv[0], qkv[1], qkv[2]
        scores = torch.einsum("bhqd,bhkd->bhqk", q, k) * (Dh ** -0.5)
        idx = torch.arange(S)
        mask = (idx[:, None] - idx[None, :] >= 0) & (idx[:, None] - idx[None, :] < W)
        scores = torch.where(mask[None, None], scores, -1e9)
        p = _softmax(scores, axis=-1)
        o = torch.einsum("bhqk,bhkd->bhqd", p, v)
        return (lambda x, *d: x.permute(*d))(o, 0, 2, 1, 3).reshape(B, S, D) @ wo

    def _B_ref(x, w1, b1, w2, b2):
        y = _layernorm(x, axis=-1)
        h = _gelu(torch.einsum("bsd,df->bsf", y, w1) + b1)
        return torch.einsum("bsf,fd->bsd", h, w2) + b2

    x = A_x
    x = x + _A_ref(_layernorm(x, axis=-1), A_wqkv, A_wo)
    x = x + _B_ref(_layernorm(x, axis=-1), B_w1, B_b1, B_w2, B_b2)
    x = x + _A_ref(_layernorm(x, axis=-1), A_wqkv, A_wo)
    x = x + _B_ref(_layernorm(x, axis=-1), B_w1, B_b1, B_w2, B_b2)
    return x
```

```cpp
#include <cuda_runtime.h>
#include <cuda.h>
#include <cuda_bf16.h>
#include <stdint.h>

#define AFTS 0
#define PROF 0

namespace {

constexpr int kD = 640, kF = 1728;
constexpr float kEps = 1e-5f;

__device__ __align__(1024) uint8_t g_wq[8 * 2 * 80 * 15 * 128];
__device__ __align__(1024) uint8_t g_wo[8 * 80 * 10 * 128];
__device__ __align__(1024) uint8_t g_w1[8 * 80 * 27 * 128];
__device__ __align__(1024) uint8_t g_w2[8 * 216 * 10 * 128];
__device__ __align__(1024) uint8_t g_x[16 * 80 * 2048];
__device__ __align__(1024) uint8_t g_o[16 * 80 * 2048];
__device__ __align__(1024) uint8_t g_h[16 * 216 * 2048];
__device__ __align__(1024) uint8_t g_kv[2 * 8 * 2 * 10 * 18 * 2048];
__device__ __align__(1024) float2 g_stats[4 * 16 * 8 * 128];
__device__ __align__(1024) float g_csq[8 * 16 * 240];
__device__ __align__(1024) float g_cs1[8 * 16 * 216];
__device__ __align__(1024) uint32_t g_flags[24 * 32];
__device__ __align__(1024) uint32_t g_epoch[132];

constexpr int FL_C = 16 * 32;

constexpr uint32_t SM_BR = 143360, QS = 19200;
constexpr uint32_t SM_RX = 0, SM_RWQ = 20480, SM_RWB = 40960;
constexpr uint32_t SM_RWO = 122880, SM_RW1 = 129280, SM_RW2 = 146560;
constexpr uint32_t SM_KV = 0, KV_HALF = 61440, KV_PLANE = 6144;
constexpr uint32_t M2S = 39936;
constexpr uint32_t SM_XS = 203776, SM_MISC = 224256;
constexpr uint32_t BAR_F = SM_MISC, BAR_E = BAR_F + 64, BAR_AF = BAR_E + 64, BAR_AT = BAR_AF + 64, BAR_KVF = BAR_AT + 16,
                   BAR_SV = BAR_KVF + 16, BAR_PUB = BAR_SV + 16, BAR_PF = BAR_PUB + 32, BAR_RAW = BAR_PF + 32,
                   SM_TPC = BAR_RAW + 16;
static_assert(SM_TPC + 4 <= SM_MISC + 384, "barriers");
constexpr uint32_t SM_CSQ = SM_MISC + 384, SM_C1B = SM_CSQ + 960, SM_B2 = SM_C1B + 1728;
constexpr uint32_t SMEM_BYTES = SM_B2 + 640;
static_assert(SMEM_BYTES <= 232448, "smem");
__device__ __forceinline__ uint32_t wo_addr(int s) { return s < 4 ? SM_BR + s * 12800 : (s == 4 ? 122880 : 81920 + (s - 5) * 12800); }
constexpr uint32_t NS = 58, N_OP = 16, N_M1 = 24, N_M2 = 40;
__device__ __forceinline__ void mbar_init(uint32_t b, uint32_t c) { asm volatile("mbarrier.init.shared::cta.b64 [%0], %1;" ::"r"(b), "r"(c)); }
__device__ __forceinline__ void mbar_expect(uint32_t b, uint32_t bytes) { asm volatile("mbarrier.arrive.expect_tx.shared::cta.b64 _, [%0], %1;" ::"r"(b), "r"(bytes) : "memory"); }
__device__ __forceinline__ void mbar_arrive(uint32_t b) { asm volatile("mbarrier.arrive.shared::cta.b64 _, [%0];" ::"r"(b) : "memory"); }
__device__ __forceinline__ void mbar_wait(uint32_t b, uint32_t ph) {
  asm volatile("{\n.reg .pred p;\n.reg .u32 n;\nmov.u32 n, 0;\nLW:\n"
               "mbarrier.try_wait.parity.shared::cta.b64 p, [%0], %1;\n@p bra LD;\n"
               "add.u32 n, n, 1;\nsetp.lt.u32 p, n, 2000000;\n@p bra LW;\ntrap;\nLD:\n}" ::"r"(b), "r"(ph) : "memory");
}
__device__ __forceinline__ bool elect() {
  uint32_t p;
  asm volatile("{.reg .pred P; elect.sync _|P, 0xffffffff; selp.u32 %0,1,0,P;}" : "=r"(p));
  return p;
}
__device__ __forceinline__ void bulk_g2s(uint32_t dst, const void* src, uint32_t bytes, uint32_t bar) {
  asm volatile("cp.async.bulk.shared::cluster.global.mbarrier::complete_tx::bytes [%0],[%1],%2,[%3];" ::"r"(dst), "l"(src), "r"(bytes), "r"(bar) : "memory");
}
__device__ __forceinline__ void st_rlx(uint32_t* p, uint32_t v) { asm volatile("st.relaxed.gpu.global.u32 [%0],%1;" ::"l"(p), "r"(v) : "memory"); }
__device__ __forceinline__ uint32_t ld_rlx(const uint32_t* p) { uint32_t v; asm volatile("ld.relaxed.gpu.global.u32 %0,[%1];" : "=r"(v) : "l"(p) : "memory"); return v; }
__device__ __forceinline__ void poll_mask(const uint32_t* p, uint32_t need, uint32_t& have, uint32_t ep, int lane) {
  if ((have & need) == need) return;
  const uint32_t* q = p + ((need | 0xffffu) >> lane & 1 ? lane : 0);
  for (int n = 0;; n++) {
    have = __ballot_sync(0xffffffffu, (int)(ld_rlx(q) - ep) >= 0);
    if ((have & need) == need) break;
    if (n > 4000000) __trap();
  }
  asm volatile("fence.acquire.gpu;\nfence.proxy.async.global;" ::: "memory");
}
__device__ __forceinline__ void poll(const uint32_t* p, int cnt, uint32_t ep, int lane) {
  uint32_t have = 0;
  poll_mask(p, cnt == 32 ? 0xffffffffu : (1u << cnt) - 1, have, ep, lane);
}
__device__ __forceinline__ void wg_fence() { asm volatile("wgmma.fence.sync.aligned;" ::: "memory"); }
__device__ __forceinline__ void wg_commit() { asm volatile("wgmma.commit_group.sync.aligned;" ::: "memory"); }
template <int N> __device__ __forceinline__ void wg_wait() { asm volatile("wgmma.wait_group.sync.aligned %0;" ::"n"(N) : "memory"); }
__device__ __forceinline__ uint32_t mkdesc(uint32_t addr, uint32_t lbo) {
  return ((addr & 0x3FFFF) >> 4) | ((lbo >> 4) << 16);
}
template <bool INIT> __device__ __forceinline__ void wgmma_n80(float (&d)[40], uint32_t da, uint32_t db) {
  if (INIT)
    asm volatile("{.reg .b64 da, db; mov.b64 da, {%40, 8}; mov.b64 db, {%41, 8};\nwgmma.mma_async.sync.aligned.m64n80k16.f32.bf16.bf16 {%0,%1,%2,%3,%4,%5,%6,%7,%8,%9,%10,%11,%12,%13,%14,%15,%16,%17,%18,%19,%20,%21,%22,%23,%24,%25,%26,%27,%28,%29,%30,%31,%32,%33,%34,%35,%36,%37,%38,%39}, da, db, 0, 1, 1, 0, 1;}"
      : "=f"(d[0]),"=f"(d[1]),"=f"(d[2]),"=f"(d[3]),"=f"(d[4]),"=f"(d[5]),"=f"(d[6]),"=f"(d[7]),"=f"(d[8]),"=f"(d[9]),"=f"(d[10]),"=f"(d[11]),"=f"(d[12]),"=f"(d[13]),"=f"(d[14]),"=f"(d[15]),"=f"(d[16]),"=f"(d[17]),"=f"(d[18]),"=f"(d[19]),"=f"(d[20]),"=f"(d[21]),"=f"(d[22]),"=f"(d[23]),"=f"(d[24]),"=f"(d[25]),"=f"(d[26]),"=f"(d[27]),"=f"(d[28]),"=f"(d[29]),"=f"(d[30]),"=f"(d[31]),"=f"(d[32]),"=f"(d[33]),"=f"(d[34]),"=f"(d[35]),"=f"(d[36]),"=f"(d[37]),"=f"(d[38]),"=f"(d[39])
      : "r"(da), "r"(db));
  else
    asm volatile("{.reg .b64 da, db; mov.b64 da, {%40, 8}; mov.b64 db, {%41, 8};\nwgmma.mma_async.sync.aligned.m64n80k16.f32.bf16.bf16 {%0,%1,%2,%3,%4,%5,%6,%7,%8,%9,%10,%11,%12,%13,%14,%15,%16,%17,%18,%19,%20,%21,%22,%23,%24,%25,%26,%27,%28,%29,%30,%31,%32,%33,%34,%35,%36,%37,%38,%39}, da, db, 1, 1, 1, 0, 1;}"
      : "+f"(d[0]),"+f"(d[1]),"+f"(d[2]),"+f"(d[3]),"+f"(d[4]),"+f"(d[5]),"+f"(d[6]),"+f"(d[7]),"+f"(d[8]),"+f"(d[9]),"+f"(d[10]),"+f"(d[11]),"+f"(d[12]),"+f"(d[13]),"+f"(d[14]),"+f"(d[15]),"+f"(d[16]),"+f"(d[17]),"+f"(d[18]),"+f"(d[19]),"+f"(d[20]),"+f"(d[21]),"+f"(d[22]),"+f"(d[23]),"+f"(d[24]),"+f"(d[25]),"+f"(d[26]),"+f"(d[27]),"+f"(d[28]),"+f"(d[29]),"+f"(d[30]),"+f"(d[31]),"+f"(d[32]),"+f"(d[33]),"+f"(d[34]),"+f"(d[35]),"+f"(d[36]),"+f"(d[37]),"+f"(d[38]),"+f"(d[39])
      : "r"(da), "r"(db));
}
template <bool INIT> __device__ __forceinline__ void wgmma_n96(float (&d)[48], uint32_t da, uint32_t db) {
  if (INIT)
    asm volatile("{.reg .b64 da, db; mov.b64 da, {%48, 8}; mov.b64 db, {%49, 8};\nwgmma.mma_async.sync.aligned.m64n96k16.f32.bf16.bf16 {%0,%1,%2,%3,%4,%5,%6,%7,%8,%9,%10,%11,%12,%13,%14,%15,%16,%17,%18,%19,%20,%21,%22,%23,%24,%25,%26,%27,%28,%29,%30,%31,%32,%33,%34,%35,%36,%37,%38,%39,%40,%41,%42,%43,%44,%45,%46,%47}, da, db, 0, 1, 1, 0, 1;}"
      : "=f"(d[0]),"=f"(d[1]),"=f"(d[2]),"=f"(d[3]),"=f"(d[4]),"=f"(d[5]),"=f"(d[6]),"=f"(d[7]),"=f"(d[8]),"=f"(d[9]),"=f"(d[10]),"=f"(d[11]),"=f"(d[12]),"=f"(d[13]),"=f"(d[14]),"=f"(d[15]),"=f"(d[16]),"=f"(d[17]),"=f"(d[18]),"=f"(d[19]),"=f"(d[20]),"=f"(d[21]),"=f"(d[22]),"=f"(d[23]),"=f"(d[24]),"=f"(d[25]),"=f"(d[26]),"=f"(d[27]),"=f"(d[28]),"=f"(d[29]),"=f"(d[30]),"=f"(d[31]),"=f"(d[32]),"=f"(d[33]),"=f"(d[34]),"=f"(d[35]),"=f"(d[36]),"=f"(d[37]),"=f"(d[38]),"=f"(d[39]),"=f"(d[40]),"=f"(d[41]),"=f"(d[42]),"=f"(d[43]),"=f"(d[44]),"=f"(d[45]),"=f"(d[46]),"=f"(d[47])
      : "r"(da), "r"(db));
  else
    asm volatile("{.reg .b64 da, db; mov.b64 da, {%48, 8}; mov.b64 db, {%49, 8};\nwgmma.mma_async.sync.aligned.m64n96k16.f32.bf16.bf16 {%0,%1,%2,%3,%4,%5,%6,%7,%8,%9,%10,%11,%12,%13,%14,%15,%16,%17,%18,%19,%20,%21,%22,%23,%24,%25,%26,%27,%28,%29,%30,%31,%32,%33,%34,%35,%36,%37,%38,%39,%40,%41,%42,%43,%44,%45,%46,%47}, da, db, 1, 1, 1, 0, 1;}"
      : "+f"(d[0]),"+f"(d[1]),"+f"(d[2]),"+f"(d[3]),"+f"(d[4]),"+f"(d[5]),"+f"(d[6]),"+f"(d[7]),"+f"(d[8]),"+f"(d[9]),"+f"(d[10]),"+f"(d[11]),"+f"(d[12]),"+f"(d[13]),"+f"(d[14]),"+f"(d[15]),"+f"(d[16]),"+f"(d[17]),"+f"(d[18]),"+f"(d[19]),"+f"(d[20]),"+f"(d[21]),"+f"(d[22]),"+f"(d[23]),"+f"(d[24]),"+f"(d[25]),"+f"(d[26]),"+f"(d[27]),"+f"(d[28]),"+f"(d[29]),"+f"(d[30]),"+f"(d[31]),"+f"(d[32]),"+f"(d[33]),"+f"(d[34]),"+f"(d[35]),"+f"(d[36]),"+f"(d[37]),"+f"(d[38]),"+f"(d[39]),"+f"(d[40]),"+f"(d[41]),"+f"(d[42]),"+f"(d[43]),"+f"(d[44]),"+f"(d[45]),"+f"(d[46]),"+f"(d[47])
      : "r"(da), "r"(db));
}
template <bool INIT> __device__ __forceinline__ void wgmma_n120(float (&d)[60], uint32_t da, uint32_t db) {
  if (INIT)
    asm volatile("{.reg .b64 da, db; mov.b64 da, {%60, 8}; mov.b64 db, {%61, 8};\nwgmma.mma_async.sync.aligned.m64n120k16.f32.bf16.bf16 {%0,%1,%2,%3,%4,%5,%6,%7,%8,%9,%10,%11,%12,%13,%14,%15,%16,%17,%18,%19,%20,%21,%22,%23,%24,%25,%26,%27,%28,%29,%30,%31,%32,%33,%34,%35,%36,%37,%38,%39,%40,%41,%42,%43,%44,%45,%46,%47,%48,%49,%50,%51,%52,%53,%54,%55,%56,%57,%58,%59}, da, db, 0, 1, 1, 0, 1;}"
      : "=f"(d[0]),"=f"(d[1]),"=f"(d[2]),"=f"(d[3]),"=f"(d[4]),"=f"(d[5]),"=f"(d[6]),"=f"(d[7]),"=f"(d[8]),"=f"(d[9]),"=f"(d[10]),"=f"(d[11]),"=f"(d[12]),"=f"(d[13]),"=f"(d[14]),"=f"(d[15]),"=f"(d[16]),"=f"(d[17]),"=f"(d[18]),"=f"(d[19]),"=f"(d[20]),"=f"(d[21]),"=f"(d[22]),"=f"(d[23]),"=f"(d[24]),"=f"(d[25]),"=f"(d[26]),"=f"(d[27]),"=f"(d[28]),"=f"(d[29]),"=f"(d[30]),"=f"(d[31]),"=f"(d[32]),"=f"(d[33]),"=f"(d[34]),"=f"(d[35]),"=f"(d[36]),"=f"(d[37]),"=f"(d[38]),"=f"(d[39]),"=f"(d[40]),"=f"(d[41]),"=f"(d[42]),"=f"(d[43]),"=f"(d[44]),"=f"(d[45]),"=f"(d[46]),"=f"(d[47]),"=f"(d[48]),"=f"(d[49]),"=f"(d[50]),"=f"(d[51]),"=f"(d[52]),"=f"(d[53]),"=f"(d[54]),"=f"(d[55]),"=f"(d[56]),"=f"(d[57]),"=f"(d[58]),"=f"(d[59])
      : "r"(da), "r"(db));
  else
    asm volatile("{.reg .b64 da, db; mov.b64 da, {%60, 8}; mov.b64 db, {%61, 8};\nwgmma.mma_async.sync.aligned.m64n120k16.f32.bf16.bf16 {%0,%1,%2,%3,%4,%5,%6,%7,%8,%9,%10,%11,%12,%13,%14,%15,%16,%17,%18,%19,%20,%21,%22,%23,%24,%25,%26,%27,%28,%29,%30,%31,%32,%33,%34,%35,%36,%37,%38,%39,%40,%41,%42,%43,%44,%45,%46,%47,%48,%49,%50,%51,%52,%53,%54,%55,%56,%57,%58,%59}, da, db, 1, 1, 1, 0, 1;}"
      : "+f"(d[0]),"+f"(d[1]),"+f"(d[2]),"+f"(d[3]),"+f"(d[4]),"+f"(d[5]),"+f"(d[6]),"+f"(d[7]),"+f"(d[8]),"+f"(d[9]),"+f"(d[10]),"+f"(d[11]),"+f"(d[12]),"+f"(d[13]),"+f"(d[14]),"+f"(d[15]),"+f"(d[16]),"+f"(d[17]),"+f"(d[18]),"+f"(d[19]),"+f"(d[20]),"+f"(d[21]),"+f"(d[22]),"+f"(d[23]),"+f"(d[24]),"+f"(d[25]),"+f"(d[26]),"+f"(d[27]),"+f"(d[28]),"+f"(d[29]),"+f"(d[30]),"+f"(d[31]),"+f"(d[32]),"+f"(d[33]),"+f"(d[34]),"+f"(d[35]),"+f"(d[36]),"+f"(d[37]),"+f"(d[38]),"+f"(d[39]),"+f"(d[40]),"+f"(d[41]),"+f"(d[42]),"+f"(d[43]),"+f"(d[44]),"+f"(d[45]),"+f"(d[46]),"+f"(d[47]),"+f"(d[48]),"+f"(d[49]),"+f"(d[50]),"+f"(d[51]),"+f"(d[52]),"+f"(d[53]),"+f"(d[54]),"+f"(d[55]),"+f"(d[56]),"+f"(d[57]),"+f"(d[58]),"+f"(d[59])
      : "r"(da), "r"(db));
}

__device__ __forceinline__ void mma16(float (&d)[4], uint32_t a0, uint32_t a1, uint32_t a2, uint32_t a3, uint32_t b0, uint32_t b1) {
  asm volatile("mma.sync.aligned.m16n8k16.row.col.f32.bf16.bf16.f32 {%0,%1,%2,%3},{%4,%5,%6,%7},{%8,%9},{%0,%1,%2,%3};"
               : "+f"(d[0]), "+f"(d[1]), "+f"(d[2]), "+f"(d[3]) : "r"(a0), "r"(a1), "r"(a2), "r"(a3), "r"(b0), "r"(b1));
}
__device__ __forceinline__ void ldsm4(uint32_t (&r)[4], uint32_t a) { asm volatile("ldmatrix.sync.aligned.m8n8.x4.shared.b16 {%0,%1,%2,%3},[%4];" : "=r"(r[0]), "=r"(r[1]), "=r"(r[2]), "=r"(r[3]) : "r"(a)); }
__device__ __forceinline__ void ldsm4t(uint32_t (&r)[4], uint32_t a) { asm volatile("ldmatrix.sync.aligned.m8n8.x4.trans.shared.b16 {%0,%1,%2,%3},[%4];" : "=r"(r[0]), "=r"(r[1]), "=r"(r[2]), "=r"(r[3]) : "r"(a)); }
__device__ __forceinline__ void ldsm2(uint32_t (&r)[2], uint32_t a) { asm volatile("ldmatrix.sync.aligned.m8n8.x2.shared.b16 {%0,%1},[%2];" : "=r"(r[0]), "=r"(r[1]) : "r"(a)); }
__device__ __forceinline__ void ldsm2t(uint32_t (&r)[2], uint32_t a) { asm volatile("ldmatrix.sync.aligned.m8n8.x2.trans.shared.b16 {%0,%1},[%2];" : "=r"(r[0]), "=r"(r[1]) : "r"(a)); }
__device__ __forceinline__ uint32_t pack(float lo, float hi) { uint32_t r; asm("cvt.rn.bf16x2.f32 %0,%1,%2;" : "=r"(r) : "f"(hi), "f"(lo)); return r; }
__device__ __forceinline__ float blo(uint32_t v) { return __uint_as_float(v << 16); }
__device__ __forceinline__ float bhi(uint32_t v) { return __uint_as_float(v & 0xffff0000u); }
__device__ __forceinline__ float ex2(float x) { float r; asm("ex2.approx.ftz.f32 %0,%1;" : "=f"(r) : "f"(x)); return r; }
__device__ __forceinline__ float tanh_fast(float x) { float r; asm("tanh.approx.f32 %0,%1;" : "=f"(r) : "f"(x)); return r; }
__device__ __forceinline__ void stg32(void* p, uint32_t v) { asm volatile("st.global.u32 [%0],%1;" ::"l"(p), "r"(v) : "memory"); }
__device__ __forceinline__ float rcp_fast(float x) { float r; asm("rcp.approx.ftz.f32 %0,%1;" : "=f"(r) : "f"(x)); return r; }
__device__ __forceinline__ void sts32(uint32_t a, uint32_t v) { asm volatile("st.shared.u32 [%0],%1;" ::"r"(a), "r"(v) : "memory"); }
__device__ __forceinline__ float2 lds64f(uint32_t a) { float2 v; asm volatile("ld.shared.v2.f32 {%0,%1},[%2];" : "=f"(v.x), "=f"(v.y) : "r"(a)); return v; }
__device__ __forceinline__ float4 lds128f(uint32_t a) { float4 v; asm volatile("ld.shared.v4.f32 {%0,%1,%2,%3},[%4];" : "=f"(v.x), "=f"(v.y), "=f"(v.z), "=f"(v.w) : "r"(a)); return v; }
__device__ __forceinline__ uint32_t ldcg32(const void* p) { uint32_t v; asm volatile("ld.relaxed.gpu.global.u32 %0,[%1];" : "=r"(v) : "l"(p) : "memory"); return v; }
__device__ __forceinline__ float2 ldcg64f(const void* p) { float2 v; asm volatile("ld.relaxed.gpu.global.v2.f32 {%0,%1},[%2];" : "=f"(v.x), "=f"(v.y) : "l"(p) : "memory"); return v; }
__device__ __forceinline__ float qsum(float v) { v += __shfl_xor_sync(0xffffffffu, v, 1); return v + __shfl_xor_sync(0xffffffffu, v, 2); }
__device__ __forceinline__ float qmax(float v) { v = fmaxf(v, __shfl_xor_sync(0xffffffffu, v, 1)); return fmaxf(v, __shfl_xor_sync(0xffffffffu, v, 2)); }

__device__ __forceinline__ void bulk_g2s_mc(uint32_t dst, const void* src, uint32_t bytes, uint32_t bar) {
  asm volatile("cp.async.bulk.shared::cluster.global.mbarrier::complete_tx::bytes.multicast::cluster [%0],[%1],%2,[%3],%4;"
               ::"r"(dst), "l"(src), "r"(bytes), "r"(bar), "h"((uint16_t)3) : "memory");
}
__device__ __forceinline__ void sts128(uint32_t a, const uint4& v) { asm volatile("st.shared.v4.u32 [%0],{%1,%2,%3,%4};" ::"r"(a), "r"(v.x), "r"(v.y), "r"(v.z), "r"(v.w) : "memory"); }
__device__ __forceinline__ void l2_prefetch(const void* p, uint32_t bytes) { asm volatile("cp.async.bulk.prefetch.L2.global [%0], %1;" ::"l"(p), "r"(bytes) : "memory"); }
__device__ __forceinline__ void tma2d(uint32_t dst, const CUtensorMap* tm, int c0, int c1, uint32_t bar) {
  asm volatile("cp.async.bulk.tensor.2d.shared::cluster.global.mbarrier::complete_tx::bytes [%0],[%1,{%3,%4}],[%2];" ::"r"(dst), "l"(tm), "r"(bar), "r"(c0), "r"(c1) : "memory");
}
__device__ __forceinline__ void tma3d(uint32_t dst, const CUtensorMap* tm, int c0, int c1, int c2, uint32_t bar) {
  asm volatile("cp.async.bulk.tensor.3d.shared::cluster.global.mbarrier::complete_tx::bytes [%0],[%1,{%3,%4,%5}],[%2];" ::"r"(dst), "l"(tm), "r"(bar), "r"(c0), "r"(c1), "r"(c2) : "memory");
}
__device__ __forceinline__ void mbar_arrive_at(uint32_t b, uint32_t cta) {
  asm volatile("{.reg .b32 r; mapa.shared::cluster.u32 r, %0, %1; mbarrier.arrive.shared::cluster.b64 _, [r];}" ::"r"(b), "r"(cta) : "memory");
}
__device__ __forceinline__ void bulk_s2g(void* dst, uint32_t src, uint32_t bytes) {
  asm volatile("cp.async.bulk.global.shared::cta.bulk_group [%0],[%1],%2;" ::"l"(dst), "r"(src), "r"(bytes) : "memory");
}
__device__ __forceinline__ void stg128(void* p, const uint4& v) { asm volatile("st.global.v4.u32 [%0],{%1,%2,%3,%4};" ::"l"(p), "r"(v.x), "r"(v.y), "r"(v.z), "r"(v.w) : "memory"); }
__device__ __forceinline__ uint4 lds128(uint32_t a) { uint4 v; asm volatile("ld.shared.v4.u32 {%0,%1,%2,%3},[%4];" : "=r"(v.x), "=r"(v.y), "=r"(v.z), "=r"(v.w) : "r"(a) : "memory"); return v; }
__device__ __forceinline__ void ldsm4m(uint32_t& r0, uint32_t& r1, uint32_t& r2, uint32_t& r3, uint32_t a) {
  asm volatile("ldmatrix.sync.aligned.m8n8.x4.shared.b16 {%0,%1,%2,%3},[%4];" : "=r"(r0), "=r"(r1), "=r"(r2), "=r"(r3) : "r"(a) : "memory");
}
__device__ __forceinline__ void stsm4(uint32_t a, uint32_t r0, uint32_t r1, uint32_t r2, uint32_t r3) {
  asm volatile("stmatrix.sync.aligned.m8n8.x4.shared.b16 [%0],{%1,%2,%3,%4};" ::"r"(a), "r"(r0), "r"(r1), "r"(r2), "r"(r3) : "memory");
}
__device__ __forceinline__ void mma8c(float (&d)[4], uint32_t a0, uint32_t a1, uint32_t b0, const float* c) {
  asm volatile("mma.sync.aligned.m16n8k8.row.col.f32.bf16.bf16.f32 {%0,%1,%2,%3},{%4,%5},{%6},{%7,%8,%9,%10};"
               : "=f"(d[0]), "=f"(d[1]), "=f"(d[2]), "=f"(d[3]) : "r"(a0), "r"(a1), "r"(b0), "f"(c[0]), "f"(c[1]), "f"(c[2]), "f"(c[3]));
}
__device__ __forceinline__ void proxy_fence() { asm volatile("fence.proxy.async.shared::cta;" ::: "memory"); }

#define TS(role, k)
#define TSC(k)
#define TSS()

__device__ __forceinline__ void wait_full(uint32_t sb, uint32_t n) { mbar_wait(sb + BAR_F + (n & 7) * 8, (n >> 3) & 1); }
__device__ __forceinline__ void wait_empty(uint32_t sb, uint32_t n) { mbar_wait(sb + BAR_E + (n & 7) * 8, (n >> 3) & 1); }
__device__ __forceinline__ void wait_pf(uint32_t sb, uint32_t k) { mbar_wait(sb + BAR_PF + (k & 3) * 8, (k >> 2) & 1); }
__device__ __forceinline__ void release(uint32_t sb, uint32_t n, int lane) { if (lane < 2 && n < 2 * NS - 5) mbar_arrive_at(sb + BAR_E + (n & 7) * 8, lane); }
__device__ __forceinline__ void publish(uint32_t sb, uint32_t k, int lane) {
  __syncwarp();
  if (lane == 0) mbar_arrive(sb + BAR_PUB + (k & 3) * 8);
}
__device__ __forceinline__ void wg_sync(int wg) { asm volatile("bar.sync %0, 128;" ::"r"(wg + 2) : "memory"); }
__device__ __forceinline__ uint32_t frag_off(int w, int lane) { return (lane >> 4) * 2048 + (16 * w + (lane & 15)) * 16; }

__device__ __forceinline__ void put_stats(const uint32_t (&xr)[20], float2* st, int lane) {
  float s0 = 0.f, s1 = 0.f;
#pragma unroll
  for (int b = 0; b < 10; b++) { s0 += blo(xr[2 * b]) + bhi(xr[2 * b]); s1 += blo(xr[2 * b + 1]) + bhi(xr[2 * b + 1]); }
  const float m0 = qsum(s0) * (1.f / 80), m1 = qsum(s1) * (1.f / 80);
  float q0 = 0.f, q1 = 0.f;
#pragma unroll
  for (int b = 0; b < 10; b++) {
    float a = blo(xr[2 * b]) - m0, bb = bhi(xr[2 * b]) - m0, cc = blo(xr[2 * b + 1]) - m1, d = bhi(xr[2 * b + 1]) - m1;
    q0 = fmaf(a, a, fmaf(bb, bb, q0));
    q1 = fmaf(cc, cc, fmaf(d, d, q1));
  }
  q0 = qsum(q0); q1 = qsum(q1);
  if ((lane & 3) == 0) { st[0] = make_float2(m0, q0); st[8] = make_float2(m1, q1); }
}
__device__ __forceinline__ void get_x(uint32_t (&xr)[20], uint32_t a) {
#pragma unroll
  for (int b = 0; b < 5; b++) ldsm4m(xr[4 * b], xr[4 * b + 1], xr[4 * b + 2], xr[4 * b + 3], a + b * 4096);
}
__device__ __forceinline__ void put_x(const uint32_t (&xr)[20], int i, int j, int w, int lane) {
  uint8_t* xd = g_x + (i * 8 + j) * 20480 + (16 * w + (lane >> 2)) * 16 + (lane & 3) * 4;
#pragma unroll
  for (int b = 0; b < 10; b++) { stg32(xd + b * 2048, xr[2 * b]); stg32(xd + b * 2048 + 128, xr[2 * b + 1]); }
}
__device__ __forceinline__ void late_x(uint32_t sb, int u, int i, int j, int w, int lane, uint32_t k) {
  uint32_t xr[20];
  get_x(xr, sb + SM_XS + frag_off(w, lane));
  put_stats(xr, g_stats + ((u * 16 + i) * 8 + j) * 128 + 16 * w + (lane >> 2), lane);
  publish(sb, k, lane);
}
struct Ln { float r0, r1, n0, n1; };
__device__ __forceinline__ void ld_parts(float (&p)[16], const float* src, int stride) {
#pragma unroll
  for (int t = 0; t < 16; t++) p[t] = __uint_as_float(ldcg32(src + t * stride));
}
__device__ __forceinline__ float sum16(const float (&p)[16]) {
  float s = 0.f;
#pragma unroll
  for (int t = 0; t < 16; t++) s += p[t];
  return s;
}
struct LnRaw { float2 a0, a1, b0, b1; };
__device__ __forceinline__ const float2* ln_ptr(int i, int w, int lane, int phase) {
  return g_stats + ((phase * 16 + i) * 8 + 2 * (lane & 3)) * 128 + 16 * w + (lane >> 2);
}
__device__ __forceinline__ LnRaw ld_ln(const float2* st) {
  LnRaw r;
  r.a0 = ldcg64f(st); r.a1 = ldcg64f(st + 128); r.b0 = ldcg64f(st + 8); r.b1 = ldcg64f(st + 136);
  return r;
}
__device__ __forceinline__ Ln get_ln(const LnRaw& raw, bool twice, float post) {
  const float2 a0 = raw.a0, a1 = raw.a1, b0 = raw.b0, b1 = raw.b1;
  const float m0 = qsum(a0.x + a1.x) * 0.125f, m1 = qsum(b0.x + b1.x) * 0.125f;
  const float d0 = a0.x - m0, d1 = a1.x - m0, e0 = b0.x - m1, e1 = b1.x - m1;
  const float v0 = qsum(a0.y + a1.y + 80.f * (d0 * d0 + d1 * d1)) * (1.f / kD), v1 = qsum(b0.y + b1.y + 80.f * (e0 * e0 + e1 * e1)) * (1.f / kD);
  Ln l;
  l.r0 = rsqrtf(v0 + kEps); l.r1 = rsqrtf(v1 + kEps);
  if (twice) {
    l.r0 *= rsqrtf(fmaf(v0 * l.r0, l.r0, kEps)) * post; l.r1 *= rsqrtf(fmaf(v1 * l.r1, l.r1, kEps)) * post;
  }
  l.n0 = -m0 * l.r0; l.n1 = -m1 * l.r1;
  return l;
}

constexpr float kNeg = -3.0e38f;
struct QF { uint32_t q[10], a0, a1, b0, b1; };
__device__ __forceinline__ void qk_unit(float (&s)[16], const QF& f, uint32_t aK, uint32_t a2, const float (&c)[8]) {
  uint32_t k0[4], k1[4], k2[2];
  ldsm2(k2, a2 + 2 * KV_PLANE);
  ldsm4(k0, aK);
  ldsm4(k1, aK + 3 * KV_PLANE);
  float(&s0)[4] = *reinterpret_cast<float(*)[4]>(&s[0]);
  float(&s1)[4] = *reinterpret_cast<float(*)[4]>(&s[4]);
  float(&s2)[4] = *reinterpret_cast<float(*)[4]>(&s[8]);
  float(&s3)[4] = *reinterpret_cast<float(*)[4]>(&s[12]);
  mma8c(s0, f.a0, f.a1, k2[0], c); mma8c(s1, f.a0, f.a1, k2[1], c);
  mma8c(s2, f.b0, f.b1, k2[0], c + 4); mma8c(s3, f.b0, f.b1, k2[1], c + 4);
  mma16(s0, f.q[0], f.q[1], f.q[2], f.q[3], k0[0], k0[1]); mma16(s1, f.q[0], f.q[1], f.q[2], f.q[3], k0[2], k0[3]);
  mma16(s2, f.q[6], f.q[7], f.q[8], f.q[9], k1[0], k1[1]); mma16(s3, f.q[6], f.q[7], f.q[8], f.q[9], k1[2], k1[3]);
}
__device__ __forceinline__ void pv_unit(float (&o)[6][4], const uint32_t (&p)[8], uint32_t aV, uint32_t a2, bool glo, uint32_t ones) {
  uint32_t v0[4], v1[4], v2[2];
  ldsm4t(v0, aV);
  ldsm4t(v1, aV + 3 * KV_PLANE);
  ldsm2t(v2, a2 + 7 * KV_PLANE);
  mma16(o[0], p[0], p[1], p[2], p[3], v0[0], v0[1]);
  mma16(o[3], p[4], p[5], p[6], p[7], v1[0], v1[1]);
  mma16(o[1], p[0], p[1], p[2], p[3], v0[2], v0[3]);
  mma16(o[4], p[4], p[5], p[6], p[7], v1[2], v1[3]);
  mma16(o[2], p[0], p[1], p[2], p[3], glo ? v2[0] : ones, glo ? v2[1] : ones);
  mma16(o[5], p[4], p[5], p[6], p[7], glo ? ones : v2[0], glo ? ones : v2[1]);
}
__device__ __forceinline__ float row_max(const float (&s)[16], int r) {
  const int b = (r >> 1) * 8 + (r & 1) * 2;
  return qmax(fmaxf(fmaxf(s[b], s[b + 1]), fmaxf(s[b + 4], s[b + 5])));
}
__device__ __forceinline__ void exp_unit(uint32_t (&p)[8], const float (&s)[16]) {
#pragma unroll
  for (int e = 0; e < 8; e++) p[e] = pack(ex2(s[2 * e]), ex2(s[2 * e + 1]));
}
constexpr float kSlack = 60.f;
struct AttC { uint32_t aK, aV, a2; int umin, tu, g, c; bool glo; };
struct AttS { float o[6][4], nm[8]; QF f; };
#define QK(S, u) qk_unit(S, a.f, k.aK + (u) * 256, k.a2 + (u) * 256, a.nm);
#define PV(P, u) pv_unit(a.o, P, k.aV + (u) * 256, k.a2 + (u) * 256, k.glo, (u) >= k.umin ? 0x3F803F80u : 0u)
#define DIAG(e) ((((e) >> 2) & 1) * 8 + 2 * k.c + ((e) & 1) <= k.g + (((e) >> 1) & 1) * 8)
__device__ __forceinline__ void att_zero(AttS& a) {
#pragma unroll
  for (int t = 0; t < 6; t++) { a.o[t][0] = a.o[t][1] = a.o[t][2] = a.o[t][3] = 0.f; }
}
__device__ __forceinline__ void att_run(AttS& a, const AttC& k, float (&s0)[16], uint32_t (&p1)[8], int u) {
#pragma unroll
  for (int t = 0; t < 8; t++) p1[t] = 0u;
  uint32_t aK = k.aK + u * 256, aV = k.aV + u * 256, a2 = k.a2 + u * 256;
  qk_unit(s0, a.f, aK, a2, a.nm);
  int thr = k.umin - u;
#pragma unroll 1
  for (int it = 0; it < 7; it++, thr += 2) {
    float s1[16];
    uint32_t p0[8];
    const uint32_t on0 = thr <= 1 ? 0x3F803F80u : 0u, on1 = thr <= 0 ? 0x3F803F80u : 0u;
    qk_unit(s1, a.f, aK - 256, a2 - 256, a.nm); pv_unit(a.o, p1, aV + 256, a2 + 256, k.glo, on0); exp_unit(p0, s0);
    qk_unit(s0, a.f, aK - 512, a2 - 512, a.nm); pv_unit(a.o, p0, aV, a2, k.glo, on1); exp_unit(p1, s1);
    aK -= 512; aV -= 512; a2 -= 512;
  }
}
__device__ __forceinline__ void merged_scores(float (&s)[16], AttS& a, const AttC& k) {
  float d[16];
  QK(s, k.tu)
  QK(d, 16 + k.tu)
#pragma unroll
  for (int e = 0; e < 16; e++) if (DIAG(e)) s[e] = d[e];
}
__device__ __forceinline__ void merged_pv(uint32_t (&p)[8], AttS& a, const AttC& k) {
  uint32_t pd[8];
#pragma unroll
  for (int e = 0; e < 4; e++) {
    const int kk = (e >> 1) * 8 + 2 * k.c, rr = k.g + (e & 1) * 8;
    const uint32_t mk = (kk <= rr ? 0xffffu : 0u) | (kk + 1 <= rr ? 0xffff0000u : 0u);
    pd[e] = p[e] & mk; pd[e + 4] = p[e + 4] & mk;
    p[e] &= ~mk; p[e + 4] &= ~mk;
  }
  PV(pd, 16 + k.tu);
  PV(p, k.tu);
}
__device__ __forceinline__ void att_tail(AttS& a, const AttC& k, const float (&s0)[16], uint32_t (&p1)[8]) {
  float s1[16];
  uint32_t p0[8];
  merged_scores(s1, a, k);
  PV(p1, k.tu + 2);
  exp_unit(p0, s0); PV(p0, k.tu + 1);
  exp_unit(p1, s1);
  merged_pv(p1, a, k);
}
__device__ __forceinline__ void att_exact(AttS& a, const AttC& k) {
  att_zero(a);
#pragma unroll
  for (int t = 0; t < 8; t++) a.nm[t] = 0.f;
#pragma unroll 1
  for (int u = k.tu; u < 16 + k.tu; u++) {
    float s[16];
    uint32_t p[8];
    if (u > k.tu) { QK(s, u) } else merged_scores(s, a, k);
    if (u < k.umin) {
#pragma unroll
      for (int e = 0; e < 16; e++) if (u > k.tu || !DIAG(e)) s[e] = kNeg;
    }
#pragma unroll
    for (int r = 0; r < 4; r++) {
      float d = row_max(s, r);
      if (u > k.tu) d = fmaxf(d, 0.f);
      const float al = u > k.tu ? ex2(-d) : 0.f;
      const int b = (r >> 1) * 8 + (r & 1) * 2;
      a.nm[2 * r] -= d; a.nm[2 * r + 1] -= d;
      s[b] -= d; s[b + 1] -= d; s[b + 4] -= d; s[b + 5] -= d;
#pragma unroll
      for (int t = 0; t < 3; t++) { a.o[(r >> 1) * 3 + t][(r & 1) * 2] *= al; a.o[(r >> 1) * 3 + t][(r & 1) * 2 + 1] *= al; }
    }
    exp_unit(p, s);
    if (u > k.tu) PV(p, u); else merged_pv(p, a, k);
  }
}
#undef QK
#undef PV
#undef DIAG
__device__ __forceinline__ void att_setq(AttS& a, const uint32_t (&q)[10], const float (&ref)[4]) {
#pragma unroll
  for (int t = 0; t < 10; t++) a.f.q[t] = q[t];
#pragma unroll
  for (int t = 0; t < 8; t++) { a.nm[t] = ref[t >> 1]; asm volatile("mov.b32 %0, %0;" : "+f"(a.nm[t])); }
  att_zero(a);
}
__device__ __forceinline__ uint32_t bfma(uint32_t a, uint32_t b, uint32_t c) { uint32_t r; asm("fma.rn.bf16x2 %0,%1,%2,%3;" : "=r"(r) : "r"(a), "r"(b), "r"(c)); return r; }
__device__ __forceinline__ void self_ref(float (&ref)[4], const uint32_t (&q)[10], const uint32_t (&kk)[10], int c) {
#pragma unroll
  for (int r = 0; r < 2; r++) {
    const uint32_t mid = bfma(q[4 + r], kk[4 + r], 0u);
    const uint32_t h0 = bfma(q[r], kk[r], bfma(q[2 + r], kk[2 + r], c < 2 ? mid : 0u));
    const uint32_t h1 = bfma(q[6 + r], kk[6 + r], bfma(q[8 + r], kk[8 + r], c < 2 ? 0u : mid));
    ref[r] = -(qsum(blo(h0) + bhi(h0)) + kSlack);
    ref[2 + r] = -(qsum(blo(h1) + bhi(h1)) + kSlack);
  }
}
__device__ __forceinline__ void att_mask(AttS& a, int c) {
  const uint32_t q4 = a.f.q[4], q5 = a.f.q[5];
  a.f.a0 = c < 2 ? q4 : 0u; a.f.a1 = c < 2 ? q5 : 0u; a.f.b0 = c < 2 ? 0u : q4; a.f.b1 = c < 2 ? 0u : q5;
}

__device__ __forceinline__ void att_out(const AttS& a, uint8_t* dst, int lane) {
  const float(&o)[6][4] = a.o;
  const int c = lane & 3;
  const float l0 = rcp_fast(__shfl_sync(0xffffffffu, o[2][0], (lane & 28) | 2)), l1 = rcp_fast(__shfl_sync(0xffffffffu, o[2][2], (lane & 28) | 2));
  const float l2 = rcp_fast(__shfl_sync(0xffffffffu, o[5][0], lane & 28)), l3 = rcp_fast(__shfl_sync(0xffffffffu, o[5][2], lane & 28));
  stg32(dst, pack(o[0][0] * l0, o[0][1] * l0)); stg32(dst + 128, pack(o[0][2] * l1, o[0][3] * l1));
  stg32(dst + 2048, pack(o[1][0] * l0, o[1][1] * l0)); stg32(dst + 2176, pack(o[1][2] * l1, o[1][3] * l1));
  stg32(dst + 4096, c < 2 ? pack(o[2][0] * l0, o[2][1] * l0) : pack(o[5][0] * l2, o[5][1] * l2));
  stg32(dst + 4224, c < 2 ? pack(o[2][2] * l1, o[2][3] * l1) : pack(o[5][2] * l3, o[5][3] * l3));
  stg32(dst + 6144, pack(o[3][0] * l2, o[3][1] * l2)); stg32(dst + 6272, pack(o[3][2] * l3, o[3][3] * l3));
  stg32(dst + 8192, pack(o[4][0] * l2, o[4][1] * l2)); stg32(dst + 8320, pack(o[4][2] * l3, o[4][3] * l3));
}

template <int B0, int B1>
__device__ __forceinline__ void kv_epi(const float (&acc)[60], uint32_t cs, uint8_t* dst, uint32_t (&kk)[10], const Ln& l) {
#pragma unroll
  for (int b = B0; b < B1; b++) {
    const float2 s = lds64f(cs + b * 32);
    const uint32_t lo = pack(fmaf(acc[4 * b], l.r0, l.n0 * s.x), fmaf(acc[4 * b + 1], l.r0, l.n0 * s.y));
    const uint32_t hi = pack(fmaf(acc[4 * b + 2], l.r1, l.n1 * s.x), fmaf(acc[4 * b + 3], l.r1, l.n1 * s.y));
    stg32(dst + (b - 5) * 36864, lo); stg32(dst + (b - 5) * 36864 + 128, hi);
    if (b < 10) { kk[2 * b - 10] = lo; kk[2 * b - 9] = hi; }
  }
}
__device__ __forceinline__ void q_epi(const float (&acc)[60], uint32_t cs, uint32_t (&q)[10], float (&ref)[4], const uint32_t (&kk)[10], const Ln& l, int c) {
  const float qs = 0.22360679774997896f * 1.4426950408889634f;
  const float r0 = l.r0 * qs, r1 = l.r1 * qs, n0 = l.n0 * qs, n1 = l.n1 * qs;
#pragma unroll
  for (int b = 0; b < 5; b++) {
    const float2 s = lds64f(cs + b * 32);
    q[2 * b] = pack(fmaf(acc[4 * b], r0, n0 * s.x), fmaf(acc[4 * b + 1], r0, n0 * s.y));
    q[2 * b + 1] = pack(fmaf(acc[4 * b + 2], r1, n1 * s.x), fmaf(acc[4 * b + 3], r1, n1 * s.y));
  }
  self_ref(ref, q, kk, c);
}

constexpr float kGa = 0.3292034911525734f, kGg = 0.7978845608028654f / kGa;
__device__ __forceinline__ float gelu2(float y) { return fmaf(y, tanh_fast(y * fmaf(y, y, kGg)), y); }
template <int B0, int B1, int N>
__device__ __forceinline__ void gelu_epi(const float (&acc)[N], uint32_t cb, uint8_t* dst, const Ln& l) {
#pragma unroll
  for (int b = B0; b < B1; b++) {
    const float4 s = lds128f(cb + b * 64);
    const float x0 = fmaf(acc[4 * b], l.r0, fmaf(l.n0, s.x, s.z)), x1 = fmaf(acc[4 * b + 1], l.r0, fmaf(l.n0, s.y, s.w));
    const float x2 = fmaf(acc[4 * b + 2], l.r1, fmaf(l.n1, s.x, s.z)), x3 = fmaf(acc[4 * b + 3], l.r1, fmaf(l.n1, s.y, s.w));
    stg32(dst + b * 2048, pack(gelu2(x0), gelu2(x1)));
    stg32(dst + b * 2048 + 128, pack(gelu2(x2), gelu2(x3)));
  }
}

__device__ __forceinline__ void add8(float (&s)[8], const uint4& v) {
  s[0] += blo(v.x); s[1] += bhi(v.x); s[2] += blo(v.y); s[3] += bhi(v.y);
  s[4] += blo(v.z); s[5] += bhi(v.z); s[6] += blo(v.w); s[7] += bhi(v.w);
}
__device__ __forceinline__ void red8(float (&s)[8]) {
#pragma unroll
  for (int e = 0; e < 8; e++) {
    s[e] += __shfl_xor_sync(0xffffffffu, s[e], 1); s[e] += __shfl_xor_sync(0xffffffffu, s[e], 2); s[e] += __shfl_xor_sync(0xffffffffu, s[e], 4);
  }
}
__device__ __forceinline__ uint4 f4u(float a, float b, float c, float d) { return make_uint4(__float_as_uint(a), __float_as_uint(b), __float_as_uint(c), __float_as_uint(d)); }

#define STAGE(N, ACC, KS, FIRST, ABASE, BBASE, PREV)                                                      \
  {                                                                                                       \
    const uint32_t dA = mkdesc(sb + (ABASE) + wg * 1024, 2048), dB = mkdesc(sb + (BBASE), (N) * 16);      \
    wait_full(sb, n); TSS();                                                                              \
    wg_fence();                                                                                           \
    wgmma_n##N<FIRST>(ACC, dA, dB);                                                                       \
    _Pragma("unroll") for (int kk = 1; kk < (KS); kk++) wgmma_n##N<false>(ACC, dA + kk * 256, dB + kk * 2 * (N)); \
    wg_commit();                                                                                          \
    wg_wait<1>();                                                                                         \
    if (PREV) release(sb, n - 1, lane);                                                                   \
    n++;                                                                                                  \
  }
#define RETIRE() { wg_wait<0>(); release(sb, n - 1, lane); }
#define P2B(s, SZ) ((s) == 2 ? 122880 : SM_BR + ((s) < 2 ? (s) : ((s) == 3 ? 2 : (s) - 4)) * (SZ))
#define NEXT3(x) x = x == 2 ? 0 : x + 1

enum { PK_O1 = 6, PK_X2, PK_S2, PK_H0, PK_H1, PK_X3, PK_S3, PK_L = 10, PK_N = 21 };

struct Maps { CUtensorMap x, wq, wo, w1, w2a, w2b; };

__global__ void __launch_bounds__(384, 1)
fused_kernel(const __grid_constant__ Maps maps, const uint8_t* __restrict__ wo, const uint8_t* __restrict__ w1, const uint8_t* __restrict__ w2,
             const __nv_bfloat16* __restrict__ b1, const __nv_bfloat16* __restrict__ b2, __nv_bfloat16* __restrict__ out) {
  const Maps* mp = &maps;
  asm volatile("" : "+l"(mp));
  const bool by_sm = gridDim.x == 132;
  extern __shared__ __align__(1024) uint8_t smem_raw[];
  uint32_t sb = (uint32_t)__cvta_generic_to_shared(smem_raw);
  asm volatile("mov.u32 %0, %0;" : "+r"(sb));
  const int tid = threadIdx.x;
  int lane = tid & 31;
  int w = __shfl_sync(0xffffffffu, tid >> 5, 0);
  uint32_t rank, tpc;
  asm("mov.u32 %0, %%cluster_ctarank;" : "=r"(rank));
  asm volatile("mov.u32 %0, %%smid;" : "=r"(tpc));
  tpc = by_sm ? tpc >> 1 : blockIdx.x >> 1;
  int i, j;
  if (!by_sm || tpc < 32) { i = by_sm ? tpc & 7 : tpc >> 3; j = by_sm ? tpc >> 3 : tpc & 7; }
  else if (tpc < 60) { i = 1 + (tpc - 32) % 7; j = 4 + (tpc - 32) / 7; }
  else { i = tpc < 62 ? -1 : 0; j = tpc - 58; }
  i = 2 * i + rank;
  if (tid == 256 && i >= 0) {
    mbar_init(sb + BAR_RAW, 1);
    mbar_init(sb + BAR_SV + 8, 1);
    mbar_expect(sb + BAR_RAW, 39680);
    tma3d(sb + SM_RWQ, &mp->wq, 80 * j, 0, 40 * i, sb + BAR_RAW);
    tma2d(sb + SM_RX, &mp->x, 80 * j, 128 * i, sb + BAR_RAW);
    mbar_expect(sb + BAR_SV + 8, 38400);
    tma3d(sb + SM_RWB, &mp->wq, 80 * j, 0, 80 * j, sb + BAR_SV + 8);
    tma3d(sb + SM_RWB + 19200, &mp->wq, 80 * j, 0, 80 * j + 40, sb + BAR_SV + 8);
    TS(1, 3);
    asm volatile("fence.mbarrier_init.release.cluster;" ::: "memory");
  }
  if (w == 0) {
    if (lane < 24) mbar_init(sb + BAR_F + 8 * lane, lane < 8 ? 2 : (lane < 16 ? 16 : 1));
    if (lane < 16 && lane != 14 && lane != 5) mbar_init(sb + BAR_AT + 8 * lane, lane < 2 ? 16 : ((lane >= 6 && lane < 10) || lane == 15 ? 8 : 1));
    if (lane == 0) sts32(sb + SM_TPC, tpc);
    asm volatile("fence.mbarrier_init.release.cluster;" ::: "memory");
  }
  __syncwarp();
  asm volatile("barrier.cluster.arrive.relaxed.aligned;\nbarrier.cluster.wait.aligned;" ::: "memory");
  if (i < 0) {
    if (w == 0) {
      const uint32_t ep = g_epoch[128 + (tpc - 60) * 2 + rank] + 32;
      for (int t = 0; t < 8; t++) poll(g_flags + FL_C + t * 32, 16, ep + 1, lane);
      if (lane == 0) g_epoch[128 + (tpc - 60) * 2 + rank] = ep;
    }
    return;
  }

  if (w >= 8) {
    asm volatile("setmaxnreg.dec.sync.aligned.u32 40;");
    const uint32_t ep = g_epoch[i * 8 + j] + 32;
    const uint32_t* frow = g_flags + i * 32;
    const uint32_t* fcol = g_flags + FL_C + j * 32;
    if (w == 8) {
      uint32_t slot = 0, have = 0;
#pragma unroll 1
      for (uint32_t n = 0, s = 0, L = 0; n < 2 * NS; n++) {
        const uint8_t* src; uint32_t dst, bytes;
        bool solo = true;
        if (s < N_OP || (s >= N_M1 && s < N_M2)) {
          const bool q = s < N_OP;
          const int t = q ? s : s - N_M1, hf = t < 2 ? t : t >= 9, r = t < 9 ? t - 2 : (t == 9 ? 6 : t - 10), ch = t < 2 ? j : (r < j ? r : r + 1);
          if (n >= 2 && n < 9) poll_mask(fcol, 3u << (2 * ch), have, ep + 1, lane);
          if (n == 9) poll(fcol, 16, ep + 2, lane);
          if (n == 2) TS(1, 0);
          if (t == 5) { if (n > 5) wait_empty(sb, n - 6); }
          else if (t >= 3) wait_empty(sb, n - (t >= 13 || (t >= 6 && t < 9) ? 4 : 3));
          else if (t == 0) { if (!q) { wait_empty(sb, n - 5); wait_full(sb, n - 4); } else if (L) wait_empty(sb, n - 4); }
          if (t == 0) slot = 0;
          bytes = !q && hf ? 15360 : 19200;
          src = (q ? g_wq + j * 307200 : g_w1 + j * 276480) + hf * 153600 + ch * bytes;
          dst = SM_BR + slot * QS;
          if (t == 12 || (t == 5)) dst = 122880; else NEXT3(slot);
        } else if (s < N_M1) {
          const int t = s - N_OP;
          if (t == 0) { if (L == 0) poll(fcol, 16, ep + 6, lane); wait_empty(sb, n - 1); mbar_wait(sb + BAR_KVF + 8, L); }
          else if (t == 5) { mbar_wait(sb + BAR_AT + 8, L); wait_pf(sb, PK_L * L + PK_O1); }
          bytes = 12800; src = g_wo + j * 102400 + t * 12800; dst = wo_addr(t); solo = false;
        } else {
          const int t = s - N_M2;
          if (t >= 5) wait_empty(sb, n - 5); else if (t < 3) wait_empty(sb, n - 5 + t);
          if (t == 0) slot = 0;
          bytes = 15360; src = g_w2 + j * 276480 + t * 15360; dst = slot * M2S + 24576; solo = false;
          slot = slot == 4 ? 0 : slot + 1;
        }
        if (elect()) {
          const uint32_t fb = sb + BAR_F + (n & 7) * 8, h = bytes >> 1;
          if (solo) mbar_arrive(fb);
          if (n < 2) mbar_arrive(fb);
          else { mbar_expect(fb, bytes); bulk_g2s_mc(sb + dst + rank * h, src + rank * h, h, fb); }
        }
        __syncwarp();
        if (++s == NS) { s = 0; L = 1; }
      }
    } else if (w == 9) {
      if (lane == 0) {
        asm volatile("prefetch.tensormap [%0];" ::"l"(&maps.w1) : "memory");
        asm volatile("prefetch.tensormap [%0];" ::"l"(&maps.w2a) : "memory");
        asm volatile("prefetch.tensormap [%0];" ::"l"(&maps.w2b) : "memory");
        asm volatile("prefetch.tensormap [%0];" ::"l"(&maps.wo) : "memory");
      }
      mbar_wait(sb + BAR_RAW + 8, 0);
#pragma unroll 1
      for (int u = 0; u < 4; u++) {
        const uint32_t L = u >> 1, n0 = NS * L + (u & 1) * N_M1;
        if (u) wait_empty(sb, n0 - 1);
        const uint32_t kx = ep + 1 + (u == 0 ? 0 : (u == 2 ? PK_X3 : PK_L * L + PK_X2));
        uint32_t have = 0;
#pragma unroll 1
        for (int s = 0; s < 7; s++) {
          const int ch = s < j ? s : s + 1;
          poll_mask(frow, 1u << ch, have, kx, lane);
          if (s == 0) TS(2, u * 8);
          if (s >= 2) mbar_wait(sb + BAR_AF + (s - 2) * 8, u & 1);
          if (s == 6) wait_empty(sb, n0 + 5);
          if (elect()) { mbar_expect(sb + BAR_AF + s * 8, 20480); bulk_g2s(sb + s * 20480, g_x + i * 163840 + ch * 20480, 20480, sb + BAR_AF + s * 8); }
          __syncwarp();
        }
        poll(frow, 8, kx + 1, lane);
        if (u == 0) poll(fcol, 16, ep + 2, lane);
        if (lane == 0) mbar_arrive(sb + BAR_SV);
        wait_empty(sb, n0 + 5);
        if (!(u & 1)) {
#pragma unroll 1
          for (int hf = 0; hf < 2; hf++) {
            wait_empty(sb, n0 + 12 + 3 * hf);
            if (u == 0 && hf) {
              if (lane == 0) {
                const int r2 = i < 8 ? 216 * i : 216 * (i - 8) + 120;
                mbar_expect(sb + BAR_RAW, i < 8 ? 42880 : 39040);
                tma2d(sb + SM_RWO, &maps.wo, 80 * j, 80 * (i & 7) + 40 * (i >> 3), sb + BAR_RAW);
                tma2d(sb + SM_RW1, &maps.w1, 216 * j, 40 * i, sb + BAR_RAW);
                tma2d(sb + SM_RW2, &maps.w2a, 80 * j, r2, sb + BAR_RAW);
                if (i < 8) tma2d(sb + SM_RW2 + 15360, &maps.w2b, 80 * j, r2 + 96, sb + BAR_RAW);
              }
              __syncwarp();
            }
            poll(fcol + max(i - 2, 0), min(i + 1, 3), ep + (L ? 14 : 3) + hf, lane);
            TS(2, u * 8 + 1 + hf);
            const uint32_t fb = sb + BAR_KVF + hf * 8;
            const uint8_t* src = g_kv + ((L * 8 + j) * 2 + hf) * 368640 + i * 2048;
            if (elect()) {
              mbar_expect(fb, 61440);
#pragma unroll 2
              for (int pl = 0; pl < 10; pl++) bulk_g2s(sb + SM_KV + hf * KV_HALF + pl * KV_PLANE, src + pl * 36864, 6144, fb);
            }
            __syncwarp();
          }
        }
        const int cnt = (u & 1) ? 18 : 8;
        uint32_t n = n0 + 16, slot = 0;
#pragma unroll 1
        for (int t = 0; t < cnt; t++, n++) {
          uint32_t dst, bytes;
          const uint8_t* src;
          if (u & 1) {
            if (t >= 5) wait_empty(sb, n - 5); else if (t < 3) wait_empty(sb, n - 5 + t);
            if (t == 0 || t == 10) { poll(frow, 8, ep + 1 + PK_L * L + PK_H0 + (t >> 3), lane); TS(2, u * 8 + 1 + (t >> 3)); }
            bytes = 24576; dst = slot * M2S; src = g_h + i * 442368 + t * 24576;
            slot = slot == 4 ? 0 : slot + 1;
          } else {
            if (t == 0 || t == 3) mbar_wait(sb + BAR_AT + (t ? 8 : 0), L);
            if (t == 3) wait_pf(sb, PK_L * L + PK_O1);
            if (t >= 4) wait_empty(sb, n - 4);
            if (!(t & 3)) have = 0;
            poll_mask(frow, 3u << ((t & 3) * 2), have, ep + 1 + (t < 4 ? (L ? 15 : 4) : PK_L * L + PK_O1), lane);
            if (!(t & 3)) TS(2, u * 8 + 3 + (t >> 2));
            bytes = 20480; dst = (t & 3) * 20480; src = g_o + i * 163840 + t * 20480;
          }
          if (elect()) { const uint32_t fb = sb + BAR_F + (n & 7) * 8; mbar_expect(fb, bytes); bulk_g2s(sb + dst, src, bytes, fb); }
          __syncwarp();
        }
      }
    } else if (w == 10) {
      if (lane == 0) {
#pragma unroll 1
        for (uint32_t k = 0; k < PK_N; k++) {
          mbar_wait(sb + BAR_PUB + (k & 3) * 8, (k >> 2) & 1);
          TS(4, 2 * k);
          if (k == 5) {
            bulk_s2g(g_wo + j * 102400 + i * 6400, sb + SM_RWO, 6400);
            bulk_s2g(g_w1 + j * 276480 + i * 9600, sb + SM_RW1, 9600);
            bulk_s2g(g_w1 + j * 276480 + 153600 + i * 7680, sb + SM_RW1 + 9600, 7680);
            bulk_s2g(g_w2 + j * 276480 + (i < 8 ? 15 * i : 120 + 12 * (i - 8)) * 1280, sb + SM_RW2, i < 8 ? 19200 : 15360);
            asm volatile("cp.async.bulk.commit_group;\ncp.async.bulk.wait_group 0;" ::: "memory");
          }
          asm volatile("fence.release.gpu;" ::: "memory");
          st_rlx(g_flags + i * 32 + j, ep + k + 1);
          st_rlx(g_flags + FL_C + j * 32 + i, ep + k + 1);
          if (k == 1) {
            const int b = i * 8 + j;
            l2_prefetch(wo + b * 6400, 6400); l2_prefetch(w1 + b * 17280, 17280); l2_prefetch(w2 + b * 17280, 17280);
            l2_prefetch(b1 + 216 * j, 432);
          }
          TS(4, 2 * k + 1);
          mbar_arrive(sb + BAR_PF + (k & 3) * 8);
        }
        g_epoch[i * 8 + j] = ep;
      }
    } else {
      uint32_t pt;
      asm volatile("{.reg .b32 r; mapa.shared::cluster.u32 r, %1, %2; ld.shared::cluster.u32 %0, [r];}" : "=r"(pt) : "r"(sb + SM_TPC), "r"(rank ^ 1) : "memory");
      if (pt != tpc) __trap();
    }
  } else {
    asm volatile("setmaxnreg.inc.sync.aligned.u32 232;");
#define FRESH() asm volatile("" : "+r"(lane), "+r"(w), "+r"(i), "+r"(j), "+r"(sb)); const int g = lane >> 2, c = lane & 3, wg = w >> 2; (void)g; (void)c; (void)wg
    TSC(0);
    {
      FRESH();
      const int r = lane & 7, q4 = lane >> 3;
      const int ngf = min(4 * w + q4, 29), hf = ngf / 15, ng = ngf % 15;
      uint4 xv[5], wv[5];
      mbar_wait(sb + BAR_RAW, 0);
      TSC(23);
#pragma unroll
      for (int t = 0; t < 5; t++) {
        const int cm = 4 * t + q4;
        wv[t] = lds128(sb + SM_RWQ + (8 * t + r) * 480 + (ng / 5) * 160 + hf * 80 + (ng % 5) * 16);
        xv[t] = lds128(sb + SM_RX + (16 * w + (cm < 10 ? 0 : 8) + r) * 160 + (cm < 10 ? cm : cm - 10) * 16);
      }
      uint8_t* wd = g_wq + j * 307200 + hf * 153600 + 5 * i * 1920 + ng * 128 + r * 16;
#pragma unroll
      for (int t = 0; t < 5; t++) if (!hf) stg128(wd + t * 1920, wv[t]);
#pragma unroll
      for (int t = 0; t < 5; t++) {
        const int cm = 4 * t + q4, xo = (cm < 10 ? cm : cm - 10) * 2048 + (16 * w + (cm < 10 ? 0 : 8) + r) * 16;
        stg128(g_x + (i * 8 + j) * 20480 + xo, xv[t]);
        sts128(sb + SM_XS + xo, xv[t]);
      }
      publish(sb, 0, lane);
      TSC(1);
      float s[8] = {0.f, 0.f, 0.f, 0.f, 0.f, 0.f, 0.f, 0.f};
#pragma unroll
      for (int t = 0; t < 5; t++) add8(s, wv[t]);
      mbar_wait(sb + BAR_SV + 8, 0);
#pragma unroll 1
      for (int h = 0; h < 2; h++) {
#pragma unroll
        for (int t = 0; t < 5; t++) xv[t] = lds128(sb + SM_RWB + (40 * h + 8 * t + r) * 480 + (ng / 5) * 160 + hf * 80 + (ng % 5) * 16);
#pragma unroll
        for (int t = 0; t < 5; t++) sts128(sb + SM_BR + hf * QS + (5 * h + t) * 1920 + ng * 128 + r * 16, xv[t]);
      }
      red8(s);
      if (r == 0) { asm volatile("st.shared.v4.f32 [%0], {%1,%2,%3,%4};" ::"r"(sb + SM_C1B + ngf * 32), "f"(s[0]), "f"(s[1]), "f"(s[2]), "f"(s[3]) : "memory");
                    asm volatile("st.shared.v4.f32 [%0], {%1,%2,%3,%4};" ::"r"(sb + SM_C1B + ngf * 32 + 16), "f"(s[4]), "f"(s[5]), "f"(s[6]), "f"(s[7]) : "memory"); }
      const float bb = __bfloat162float(b2[80 * j + min(tid, 79)]);
      if (tid < 80) { sts32(sb + SM_B2 + tid * 4, 0u); sts32(sb + SM_B2 + 320 + tid * 4, __float_as_uint(bb)); }
      proxy_fence();
      asm volatile("bar.sync 1, 256;" ::: "memory");
      if (lane == 0) mbar_arrive(sb + BAR_RAW + 8);
      {
        wait_pf(sb, 0);
#pragma unroll
        for (int t = 0; t < 5; t++) if (hf) stg128(wd + t * 1920, wv[t]);
      }
    }
    uint32_t n = 0;
#pragma unroll 1
    for (int u = 0; u < 4; u++) {
      const int L = u >> 1;
      const uint32_t pk = PK_L * L;
      float acc[40];
      if (!(u & 1)) {
        AttS a, b;
        {
          FRESH();
          float a0[60], a1[60];
          STAGE(120, a0, 5, true, SM_XS, SM_BR, false)
          STAGE(120, a1, 5, true, SM_XS, SM_BR + QS, true)
          if (u == 0 && tid < 60) stg128(g_csq + (j * 16 + i) * 240 + tid * 4, lds128(sb + SM_C1B + tid * 16));
          late_x(sb, u, i, j, w, lane, u ? PK_S3 : 1);
          RETIRE()
          const uint32_t cs = sb + SM_CSQ + c * 8;
          uint8_t* kd = g_kv + (L * 8 + j) * 737280 + (i + 2) * 2048 + (16 * w + g) * 16 + c * 4;
          const float2* stp = ln_ptr(i, w, lane, u);
          asm volatile("" : "+l"(kd), "+l"(stp));
          uint32_t slot = 2;
#pragma unroll 1
          for (int s = 0; s < 7; s++) {
            mbar_wait(sb + BAR_AF + s * 8, 0);
            STAGE(120, a0, 5, false, s * 20480, s == 3 ? 122880 : SM_BR + slot * QS, s)
            if (s != 3) NEXT3(slot);
          }
          TSC(3 + L * 24);
          mbar_wait(sb + BAR_SV, 0);
          const LnRaw raw = ld_ln(stp);
          float part[16] = {};
          if (u == 0) ld_parts(part, g_csq + j * 3840 + min(w * 32 + lane, 239), 240);
          uint32_t q[10], kk[10];
          float ref[4];
          STAGE(120, a1, 5, false, 122880, SM_BR + 2 * QS, true)
          if (u == 0) {
            if (w * 32 + lane < 240) sts32(sb + SM_CSQ + (w * 32 + lane) * 4, __float_as_uint(sum16(part)));
            asm volatile("bar.sync 1, 256;" ::: "memory");
          }
          const Ln ln = get_ln(raw, false, 1.f);
          kv_epi<5, 8>(a0, cs, kd, kk, ln);
          RETIRE()
          kv_epi<8, 15>(a0, cs, kd, kk, ln);
          publish(sb, L ? 13 : 2, lane);
          STAGE(120, a1, 5, false, 0, P2B(0, QS), false)
          q_epi(a0, cs, q, ref, kk, ln, c);
          att_setq(a, q, ref);
          TSC(21 + L * 24);
#pragma unroll 1
          for (int s = 1; s < 6; s++) STAGE(120, a1, 5, false, s * 20480, P2B(s, QS), true)
          wg_wait<0>();
          release(sb, n - 1, lane);
          TSC(4 + L * 24);
          kv_epi<5, 15>(a1, cs + 480, kd + 368640, kk, ln);
          publish(sb, L ? 14 : 3, lane);
          q_epi(a1, cs + 480, q, ref, kk, ln, c);
          att_setq(b, q, ref);
        }
        TSC(5 + L * 24);
        {
          FRESH();
          AttC k;
          k.aK = sb + SM_KV + ((lane >> 3) & 1) * KV_PLANE + (((lane >> 4) & 1) * 8 + (lane & 7)) * 16;
          k.aV = sb + SM_KV + 5 * KV_PLANE + ((lane >> 4) & 1) * KV_PLANE + (lane & 15) * 16;
          k.a2 = sb + SM_KV + (lane & 15) * 16;
          k.umin = i >= 2 ? 0 : 16 - 8 * i; k.tu = w; k.g = g; k.c = c; k.glo = g < 4;
#pragma unroll 1
          for (int hf = 0; hf < 2; hf++) {
            float s0[16];
            uint32_t p1[8];
            att_mask(a, c);
            mbar_wait(sb + BAR_KVF + hf * 8, L);
            if (hf == 0) TSC(22 + L * 24);
            att_run(a, k, s0, p1, 15 + w);
            att_tail(a, k, s0, p1);
            const float la = c < 2 ? a.o[5][0] : a.o[2][0], lb = c < 2 ? a.o[5][2] : a.o[2][2];
            if (__any_sync(0xffffffffu, !(la < 2.f && lb < 2.f && la > 7.9e-31f && lb > 7.9e-31f))) {
              att_exact(a, k);
            }
            att_out(a, g_o + (i * 80 + hf * 40 + j * 5) * 2048 + (16 * w + g) * 16 + c * 4, lane);
            publish(sb, hf ? pk + PK_O1 : (L ? 15 : 4), lane);
            if (lane < 2) mbar_arrive_at(sb + BAR_AT + hf * 8, lane);
            a = b;
            k.aK += KV_HALF; k.aV += KV_HALF; k.a2 += KV_HALF;
            TSC(6 + hf + L * 24);
            if (u == 0 && hf == 0) {
              const int r = lane & 7, tc = w * 32 + lane, cnt2 = i < 8 ? 1200 : 960;
              const int hf1 = w >> 2, ng1 = 4 * (w & 3) + (lane >> 3), NG1 = 15 - 3 * hf1;
              const bool ok1 = ng1 < NG1;
              uint4 v1[5], v2[5], vo[2];
              mbar_wait(sb + BAR_RAW, 1);
#pragma unroll
              for (int t = 0; t < 5; t++) {
                const int cm = min(t * 256 + tc, cnt2 - 1) >> 3;
                v1[t] = lds128(sb + SM_RW1 + (8 * t + r) * 432 + hf1 * 240 + (ok1 ? ng1 : 0) * 16);
                v2[t] = lds128(sb + SM_RW2 + (cm / 10 * 8 + r) * 160 + (cm % 10) * 16);
              }
#pragma unroll
              for (int t = 0; t < 2; t++) { const int cm = min(t * 256 + tc, 399) >> 3; vo[t] = lds128(sb + SM_RWO + (cm / 10 * 8 + r) * 160 + (cm % 10) * 16); }
              asm volatile("bar.sync 1, 256;" ::: "memory");
              float sm[8] = {0.f, 0.f, 0.f, 0.f, 0.f, 0.f, 0.f, 0.f};
#pragma unroll
              for (int t = 0; t < 5; t++) {
                if (ok1) sts128(sb + SM_RW1 + hf1 * 9600 + (t * NG1 + ng1) * 128 + r * 16, v1[t]);
                if (t * 256 + tc < cnt2) sts128(sb + SM_RW2 + (t * 256 + tc) * 16, v2[t]);
                if (t < 2 && t * 256 + tc < 400) sts128(sb + SM_RWO + (t * 256 + tc) * 16, vo[t]);
                add8(sm, v1[t]);
              }
              proxy_fence();
              red8(sm);
              float* cd = g_cs1 + (j * 16 + i) * 216 + 120 * hf1 + 8 * ng1;
              if (ok1 && r == 0) { stg128(cd, f4u(sm[0], sm[1], sm[2], sm[3])); stg128(cd + 4, f4u(sm[4], sm[5], sm[6], sm[7])); }
              publish(sb, 5, lane);
              TSC(2);
            }
          }
        }
        {
          FRESH();
          STAGE(80, acc, 5, true, 0, SM_BR, false)
#pragma unroll 1
          for (int s = 1; s < 8; s++) {
            if (u == 0 && s == 3) {
              const int col = min(w * 32 + lane, 215);
              float part[16];
              ld_parts(part, g_cs1 + j * 3456 + col, 216);
              const uint32_t ad = sb + SM_C1B + (col >> 1) * 16 + (col & 1) * 4;
              sts32(ad + 8, __float_as_uint(__bfloat162float(b1[216 * j + col]) * kGa));
              sts32(ad, __float_as_uint(sum16(part)));
              asm volatile("bar.sync 1, 256;" ::: "memory");
            }
            STAGE(80, acc, 5, false, (s & 3) * 20480, wo_addr(s), true)
          }
        }
      } else {
        FRESH();
        float a0[60], a1[48];
        STAGE(120, a0, 5, true, SM_XS, SM_BR, false)
        STAGE(96, a1, 5, true, SM_XS, SM_BR + QS, true)
        late_x(sb, u, i, j, w, lane, pk + PK_S2);
        RETIRE()
        const uint32_t cb = sb + SM_C1B + c * 16;
        uint8_t* hd = g_h + (i * 216 + j * 15) * 2048 + (16 * w + g) * 16 + c * 4;
        const float2* stp = ln_ptr(i, w, lane, u);
        asm volatile("" : "+l"(hd), "+l"(stp));
        uint32_t slot = 2;
#pragma unroll 1
        for (int s = 0; s < 7; s++) {
          mbar_wait(sb + BAR_AF + s * 8, 1);
          STAGE(120, a0, 5, false, s * 20480, s == 3 ? 122880 : SM_BR + slot * QS, s)
          if (s != 3) NEXT3(slot);
        }
        TSC(12 + L * 24);
        mbar_wait(sb + BAR_SV, 1);
        const LnRaw raw = ld_ln(stp);
        STAGE(96, a1, 5, false, 122880, SM_BR + 2 * QS, true)
        const Ln ln = get_ln(raw, true, kGa);
        gelu_epi<0, 6>(a0, cb, hd, ln);
        STAGE(96, a1, 5, false, 0, P2B(0, QS), true)
        gelu_epi<6, 15>(a0, cb, hd, ln);
        publish(sb, pk + PK_H0, lane);
        TSC(14 + L * 24);
#pragma unroll 1
        for (int s = 1; s < 6; s++) STAGE(96, a1, 5, false, s * 20480, P2B(s, QS), true)
        hd += (120 - 3 * j) * 2048;
        RETIRE()
        TSC(13 + L * 24);
        gelu_epi<0, 5>(a1, cb + 960, hd, ln);
        STAGE(80, acc, 6, true, 0, 24576, false)
        gelu_epi<5, 12>(a1, cb + 960, hd, ln);
        publish(sb, pk + PK_H1, lane);
        TSC(15 + L * 24);
        slot = 1;
#pragma unroll 1
        for (int s = 1; s < 18; s++) {
          STAGE(80, acc, 6, false, slot * M2S, slot * M2S + 24576, true)
          slot = slot == 4 ? 0 : slot + 1;
        }
      }
      {
        FRESH();
        uint32_t xr[20];
        const uint32_t xa = sb + SM_XS + frag_off(w, lane);
        get_x(xr, xa);
        float xa0[20], xa1[20];
        const float sc = (u & 1) ? 0.5f / kGa : 1.f;
#pragma unroll
        for (int b = 0; b < 10; b++) {
          xa0[2 * b] = blo(xr[2 * b]); xa1[2 * b] = bhi(xr[2 * b]);
          xa0[2 * b + 1] = blo(xr[2 * b + 1]); xa1[2 * b + 1] = bhi(xr[2 * b + 1]);
        }
        if (u & 1) {
#pragma unroll
          for (int b = 0; b < 10; b++) {
            const float2 bv = lds64f(sb + SM_B2 + (u & 1) * 320 + b * 32 + c * 8);
            xa0[2 * b] += bv.x; xa1[2 * b] += bv.y; xa0[2 * b + 1] += bv.x; xa1[2 * b + 1] += bv.y;
          }
        }
        wg_wait<0>();
        release(sb, n - 1, lane);
        TSC(10 + (u & 1) * 8 + L * 24);
#pragma unroll
        for (int b = 0; b < 10; b++) {
          xr[2 * b] = pack(fmaf(acc[4 * b], sc, xa0[2 * b]), fmaf(acc[4 * b + 1], sc, xa1[2 * b]));
          xr[2 * b + 1] = pack(fmaf(acc[4 * b + 2], sc, xa0[2 * b + 1]), fmaf(acc[4 * b + 3], sc, xa1[2 * b + 1]));
        }
        if (u == 3) {
          uint8_t* od = (uint8_t*)(out + (128 * i + 16 * w + g) * kD + 80 * j) + (c & 1) * 16 + (c >> 1) * 8;
#pragma unroll
          for (int b = 0; b < 10; b += 2)
#pragma unroll
            for (int h = 0; h < 2; h++) {
              const uint32_t mine = (c & 1) ? xr[2 * b + 2 + h] : xr[2 * b + h], give = (c & 1) ? xr[2 * b + h] : xr[2 * b + 2 + h];
              const uint32_t got = __shfl_xor_sync(0xffffffffu, give, 1);
              asm volatile("st.global.v2.u32 [%0],{%1,%2};" ::"l"(od + h * 16 * kD + b * 16), "r"((c & 1) ? got : mine), "r"((c & 1) ? mine : got) : "memory");
            }
          TSC(43);
          break;
        }
        put_x(xr, i, j, w, lane);
        publish(sb, pk + ((u & 1) ? PK_X3 : PK_X2), lane);
#pragma unroll
        for (int b = 0; b < 5; b++) stsm4(xa + b * 4096, xr[4 * b], xr[4 * b + 1], xr[4 * b + 2], xr[4 * b + 3]);
        proxy_fence();
        wg_sync(wg);
      }
      TSC(11 + (u & 1) * 8 + L * 24);
    }
  }
}

}

typedef CUresult (*EncodeFn)(CUtensorMap*, CUtensorMapDataType, cuuint32_t, void*, const cuuint64_t*, const cuuint64_t*, const cuuint32_t*,
                             const cuuint32_t*, CUtensorMapInterleave, CUtensorMapSwizzle, CUtensorMapL2promotion, CUtensorMapFloatOOBfill);

extern "C" void kernel_launch(void* const* d_in, const int* in_sizes, int n_in, void* d_out, int out_size) {
  (void)in_sizes; (void)n_in; (void)out_size;
  EncodeFn enc = nullptr;
  cudaDriverEntryPointQueryResult qr;
  cudaGetDriverEntryPoint("cuTensorMapEncodeTiled", (void**)&enc, cudaEnableDefault, &qr);
  Maps maps;
  auto mk = [&](CUtensorMap* m, void* p, int rank, cuuint64_t d0, cuuint64_t d1, cuuint64_t d2, cuuint64_t s1, cuuint64_t s2, cuuint32_t b0, cuuint32_t b1, cuuint32_t b2) {
    const cuuint64_t dims[3] = {d0, d1, d2}, strides[2] = {s1, s2};
    const cuuint32_t box[3] = {b0, b1, b2}, es[3] = {1, 1, 1};
    enc(m, CU_TENSOR_MAP_DATA_TYPE_BFLOAT16, rank, p, dims, strides, box, es, CU_TENSOR_MAP_INTERLEAVE_NONE, CU_TENSOR_MAP_SWIZZLE_NONE,
        CU_TENSOR_MAP_L2_PROMOTION_L2_128B, CU_TENSOR_MAP_FLOAT_OOB_FILL_NONE);
  };
  mk(&maps.x, d_in[0], 2, kD, 2048, 1, kD * 2, 0, 80, 128, 1);
  mk(&maps.wq, d_in[1], 3, kD, 3, kD, kD * 2, kD * 6, 80, 3, 40);
  mk(&maps.wo, d_in[2], 2, kD, kD, 1, kD * 2, 0, 80, 40, 1);
  mk(&maps.w1, d_in[4], 2, kF, kD, 1, kF * 2, 0, 216, 40, 1);
  mk(&maps.w2a, d_in[6], 2, kD, kF, 1, kD * 2, 0, 80, 96, 1);
  mk(&maps.w2b, d_in[6], 2, kD, kF, 1, kD * 2, 0, 80, 24, 1);

  cudaFuncSetAttribute(fused_kernel, cudaFuncAttributeMaxDynamicSharedMemorySize, SMEM_BYTES);
  cudaLaunchConfig_t cfg = {};
  cudaLaunchAttribute at[1];
  at[0].id = cudaLaunchAttributeClusterDimension;
  at[0].val.clusterDim.x = 2; at[0].val.clusterDim.y = 1; at[0].val.clusterDim.z = 1;
  cfg.gridDim = dim3(132); cfg.blockDim = dim3(384); cfg.dynamicSmemBytes = SMEM_BYTES; cfg.stream = cudaStreamPerThread;
  cfg.attrs = at; cfg.numAttrs = 1;
  int sms = 0, ncl = 0;
  cudaDeviceGetAttribute(&sms, cudaDevAttrMultiProcessorCount, 0);
  cudaOccupancyMaxActiveClusters(&ncl, fused_kernel, &cfg);
  if (sms != 132 || ncl != 66) cfg.gridDim = dim3(128);
  cudaLaunchKernelEx(&cfg, fused_kernel, maps, (const uint8_t*)d_in[2], (const uint8_t*)d_in[4], (const uint8_t*)d_in[6], (const __nv_bfloat16*)d_in[5], (const __nv_bfloat16*)d_in[7], (__nv_bfloat16*)d_out);
}
```
